```python
import torch

def _softmax(x, axis=-1):
    return torch.softmax(x, dim=axis)
def _gelu(x):
    return torch.nn.functional.gelu(x, approximate="tanh")
def _silu(x):
    return torch.nn.functional.silu(x)
def _sigmoid(x):
    return torch.sigmoid(x)
def _layernorm(x, axis=-1, eps=1e-5):
    m = x.mean(dim=axis, keepdim=True)
    v = x.var(dim=axis, keepdim=True, unbiased=False)
    return (x - m) / torch.sqrt(v + eps)
def _scatter_add(tgt, idx, src, axis=0):
    return tgt.clone().index_add_(axis, idx, src)
def _segment_sum(src, seg, n):
    out = torch.zeros((n,) + src.shape[1:], dtype=src.dtype)
    return out.index_add_(0, seg, src)
def _pad(x, pw):
    flat = tuple(v for pair in reversed(pw) for v in pair)
    return torch.nn.functional.pad(x, flat)

kernel_name = 'sequential_preLN__sliding_block__dense_activation_squared_relu__prompt'

def setup_inputs():

    _w = (lambda a: (lambda t: t.to(torch.bfloat16) if t.is_floating_point() else t)(torch.as_tensor(a)))
    def _A_setup():
        B, S, D = 1, 2048, 640
        return {
            "x": _w((lambda *s: torch.randn(*s, dtype=torch.bfloat16) * 0.05)(B, S, D)),
            "wqkv": _w((lambda *s: torch.randn(*s, dtype=torch.bfloat16) * 0.05)(D, 3 * D)),
            "wo": _w((lambda *s: torch.randn(*s, dtype=torch.bfloat16) * 0.05)(D, D)),
        }
    _A_in = _A_setup()

    def _B_setup():
        B, S, D, F = 1, 2048, 640, 1536
        return {
            "x": _w((lambda *s: torch.randn(*s, dtype=torch.bfloat16) * 0.05)(B, S, D)),
            "w1": _w((lambda *s: torch.randn(*s, dtype=torch.bfloat16) * 0.05)(D, F)),
            "b1": _w((lambda *s: torch.randn(*s, dtype=torch.bfloat16) * 0.4)(F)),
            "w2": _w((lambda *s: torch.randn(*s, dtype=torch.bfloat16) * 0.05)(F, D)),
            "b2": _w((lambda *s: torch.randn(*s, dtype=torch.bfloat16) * 3.2)(D)),
        }
    _B_in = _B_setup()

    return {
        "A_x": _A_in["x"],
        "A_wqkv": _A_in["wqkv"],
        "A_wo": _A_in["wo"],
        "B_x": _B_in["x"],
        "B_w1": _B_in["w1"],
        "B_b1": _B_in["b1"],
        "B_w2": _B_in["w2"],
        "B_b2": _B_in["b2"],
    }

def reference(A_x, A_wqkv, A_wo, B_x, B_w1, B_b1, B_w2, B_b2):
    def _A_ref(x, wqkv, wo):
        B, S, D = x.shape
        H = 32; Dh = D // H; W = 256
        qkv = (lambda x, *d: x.permute(*d))((x @ wqkv).reshape(B, S, 3, H, Dh), 2, 0, 3, 1, 4)
        q, k, v = qkv[0], qkv[1], qkv[2]
        scores = torch.einsum("bhqd,bhkd->bhqk", q, k) * (Dh ** -0.5)
        idx = torch.arange(S)
        mask = (idx[:, None] - idx[None, :] >= 0) & (idx[:, None] - idx[None, :] < W)
        scores = torch.where(mask[None, None], scores, -1e9)
        p = _softmax(scores, axis=-1)
        o = torch.einsum("bhqk,bhkd->bhqd", p, v)
        return (lambda x, *d: x.permute(*d))(o, 0, 2, 1, 3).reshape(B, S, D) @ wo

    def _B_ref(x, w1, b1, w2, b2):
        h = torch.einsum("bsd,df->bsf", x, w1) + b1
        zero = torch.zeros_like(h)
        r = torch.where(h > zero, h, zero)
        h = r * r
        out = torch.einsum("bsf,fd->bsd", h, w2) + b2
        return out

    x = A_x
    h = x + _A_ref(_layernorm(x, axis=-1), A_wqkv, A_wo)
    h2 = h + _B_ref(_layernorm(h, axis=-1), B_w1, B_b1, B_w2, B_b2)
    return h2
```

```cpp
#include <cuda_runtime.h>
#include <cuda_bf16.h>
#include <cuda.h>
#include <stdint.h>

namespace {

__device__ __forceinline__ void wgmma_ss_n192_tb(float (&d)[96], uint64_t da, uint64_t db, int scale_d) {
    asm volatile("{\n.reg .pred p;\nsetp.ne.b32 p, %98, 0;\n"
        "wgmma.mma_async.sync.aligned.m64n192k16.f32.bf16.bf16 "
        "{%0, %1, %2, %3, %4, %5, %6, %7, %8, %9, %10, %11, %12, %13, %14, %15, "
        "%16, %17, %18, %19, %20, %21, %22, %23, %24, %25, %26, %27, %28, %29, %30, %31, "
        "%32, %33, %34, %35, %36, %37, %38, %39, %40, %41, %42, %43, %44, %45, %46, %47, "
        "%48, %49, %50, %51, %52, %53, %54, %55, %56, %57, %58, %59, %60, %61, %62, %63, "
        "%64, %65, %66, %67, %68, %69, %70, %71, %72, %73, %74, %75, %76, %77, %78, %79, "
        "%80, %81, %82, %83, %84, %85, %86, %87, %88, %89, %90, %91, %92, %93, %94, %95}, "
        "%96, %97, p, 1, 1, 0, 1;\n}\n"
        : "+f"(d[0]), "+f"(d[1]), "+f"(d[2]), "+f"(d[3]), "+f"(d[4]), "+f"(d[5]), "+f"(d[6]), "+f"(d[7]),
          "+f"(d[8]), "+f"(d[9]), "+f"(d[10]), "+f"(d[11]), "+f"(d[12]), "+f"(d[13]), "+f"(d[14]), "+f"(d[15]),
          "+f"(d[16]), "+f"(d[17]), "+f"(d[18]), "+f"(d[19]), "+f"(d[20]), "+f"(d[21]), "+f"(d[22]), "+f"(d[23]),
          "+f"(d[24]), "+f"(d[25]), "+f"(d[26]), "+f"(d[27]), "+f"(d[28]), "+f"(d[29]), "+f"(d[30]), "+f"(d[31]),
          "+f"(d[32]), "+f"(d[33]), "+f"(d[34]), "+f"(d[35]), "+f"(d[36]), "+f"(d[37]), "+f"(d[38]), "+f"(d[39]),
          "+f"(d[40]), "+f"(d[41]), "+f"(d[42]), "+f"(d[43]), "+f"(d[44]), "+f"(d[45]), "+f"(d[46]), "+f"(d[47]),
          "+f"(d[48]), "+f"(d[49]), "+f"(d[50]), "+f"(d[51]), "+f"(d[52]), "+f"(d[53]), "+f"(d[54]), "+f"(d[55]),
          "+f"(d[56]), "+f"(d[57]), "+f"(d[58]), "+f"(d[59]), "+f"(d[60]), "+f"(d[61]), "+f"(d[62]), "+f"(d[63]),
          "+f"(d[64]), "+f"(d[65]), "+f"(d[66]), "+f"(d[67]), "+f"(d[68]), "+f"(d[69]), "+f"(d[70]), "+f"(d[71]),
          "+f"(d[72]), "+f"(d[73]), "+f"(d[74]), "+f"(d[75]), "+f"(d[76]), "+f"(d[77]), "+f"(d[78]), "+f"(d[79]),
          "+f"(d[80]), "+f"(d[81]), "+f"(d[82]), "+f"(d[83]), "+f"(d[84]), "+f"(d[85]), "+f"(d[86]), "+f"(d[87]),
          "+f"(d[88]), "+f"(d[89]), "+f"(d[90]), "+f"(d[91]), "+f"(d[92]), "+f"(d[93]), "+f"(d[94]), "+f"(d[95])
        : "l"(da), "l"(db), "r"(scale_d));
}
__device__ __forceinline__ void wgmma_ss_n48_tb(float (&d)[24], uint64_t da, uint64_t db, int scale_d) {
    asm volatile("{\n.reg .pred p;\nsetp.ne.b32 p, %26, 0;\n"
        "wgmma.mma_async.sync.aligned.m64n48k16.f32.bf16.bf16 "
        "{%0, %1, %2, %3, %4, %5, %6, %7, %8, %9, %10, %11, %12, %13, %14, %15, "
        "%16, %17, %18, %19, %20, %21, %22, %23}, "
        "%24, %25, p, 1, 1, 0, 1;\n}\n"
        : "+f"(d[0]), "+f"(d[1]), "+f"(d[2]), "+f"(d[3]), "+f"(d[4]), "+f"(d[5]), "+f"(d[6]), "+f"(d[7]),
          "+f"(d[8]), "+f"(d[9]), "+f"(d[10]), "+f"(d[11]), "+f"(d[12]), "+f"(d[13]), "+f"(d[14]), "+f"(d[15]),
          "+f"(d[16]), "+f"(d[17]), "+f"(d[18]), "+f"(d[19]), "+f"(d[20]), "+f"(d[21]), "+f"(d[22]), "+f"(d[23])
        : "l"(da), "l"(db), "r"(scale_d));
}
__device__ __forceinline__ void wgmma_ss_n160_tb(float (&d)[80], uint64_t da, uint64_t db, int scale_d) {
    asm volatile("{\n.reg .pred p;\nsetp.ne.b32 p, %82, 0;\n"
        "wgmma.mma_async.sync.aligned.m64n160k16.f32.bf16.bf16 "
        "{%0, %1, %2, %3, %4, %5, %6, %7, %8, %9, %10, %11, %12, %13, %14, %15, "
        "%16, %17, %18, %19, %20, %21, %22, %23, %24, %25, %26, %27, %28, %29, %30, %31, "
        "%32, %33, %34, %35, %36, %37, %38, %39, %40, %41, %42, %43, %44, %45, %46, %47, "
        "%48, %49, %50, %51, %52, %53, %54, %55, %56, %57, %58, %59, %60, %61, %62, %63, "
        "%64, %65, %66, %67, %68, %69, %70, %71, %72, %73, %74, %75, %76, %77, %78, %79}, "
        "%80, %81, p, 1, 1, 0, 1;\n}\n"
        : "+f"(d[0]), "+f"(d[1]), "+f"(d[2]), "+f"(d[3]), "+f"(d[4]), "+f"(d[5]), "+f"(d[6]), "+f"(d[7]),
          "+f"(d[8]), "+f"(d[9]), "+f"(d[10]), "+f"(d[11]), "+f"(d[12]), "+f"(d[13]), "+f"(d[14]), "+f"(d[15]),
          "+f"(d[16]), "+f"(d[17]), "+f"(d[18]), "+f"(d[19]), "+f"(d[20]), "+f"(d[21]), "+f"(d[22]), "+f"(d[23]),
          "+f"(d[24]), "+f"(d[25]), "+f"(d[26]), "+f"(d[27]), "+f"(d[28]), "+f"(d[29]), "+f"(d[30]), "+f"(d[31]),
          "+f"(d[32]), "+f"(d[33]), "+f"(d[34]), "+f"(d[35]), "+f"(d[36]), "+f"(d[37]), "+f"(d[38]), "+f"(d[39]),
          "+f"(d[40]), "+f"(d[41]), "+f"(d[42]), "+f"(d[43]), "+f"(d[44]), "+f"(d[45]), "+f"(d[46]), "+f"(d[47]),
          "+f"(d[48]), "+f"(d[49]), "+f"(d[50]), "+f"(d[51]), "+f"(d[52]), "+f"(d[53]), "+f"(d[54]), "+f"(d[55]),
          "+f"(d[56]), "+f"(d[57]), "+f"(d[58]), "+f"(d[59]), "+f"(d[60]), "+f"(d[61]), "+f"(d[62]), "+f"(d[63]),
          "+f"(d[64]), "+f"(d[65]), "+f"(d[66]), "+f"(d[67]), "+f"(d[68]), "+f"(d[69]), "+f"(d[70]), "+f"(d[71]),
          "+f"(d[72]), "+f"(d[73]), "+f"(d[74]), "+f"(d[75]), "+f"(d[76]), "+f"(d[77]), "+f"(d[78]), "+f"(d[79])
        : "l"(da), "l"(db), "r"(scale_d));
}
__device__ __forceinline__ void wgmma_rs_n64(float (&d)[32], uint32_t a0, uint32_t a1, uint32_t a2, uint32_t a3, uint64_t db, int scale_d) {
    asm volatile("{\n.reg .pred p;\nsetp.ne.b32 p, %37, 0;\n"
        "wgmma.mma_async.sync.aligned.m64n64k16.f32.bf16.bf16 "
        "{%0, %1, %2, %3, %4, %5, %6, %7, %8, %9, %10, %11, %12, %13, %14, %15, "
        "%16, %17, %18, %19, %20, %21, %22, %23, %24, %25, %26, %27, %28, %29, %30, %31}, "
        "{%32, %33, %34, %35}, %36, p, 1, 1, 0;\n}\n"
        : "+f"(d[0]), "+f"(d[1]), "+f"(d[2]), "+f"(d[3]), "+f"(d[4]), "+f"(d[5]), "+f"(d[6]), "+f"(d[7]),
          "+f"(d[8]), "+f"(d[9]), "+f"(d[10]), "+f"(d[11]), "+f"(d[12]), "+f"(d[13]), "+f"(d[14]), "+f"(d[15]),
          "+f"(d[16]), "+f"(d[17]), "+f"(d[18]), "+f"(d[19]), "+f"(d[20]), "+f"(d[21]), "+f"(d[22]), "+f"(d[23]),
          "+f"(d[24]), "+f"(d[25]), "+f"(d[26]), "+f"(d[27]), "+f"(d[28]), "+f"(d[29]), "+f"(d[30]), "+f"(d[31])
        : "r"(a0), "r"(a1), "r"(a2), "r"(a3), "l"(db), "r"(scale_d));
}
__device__ __forceinline__ void wgmma_rs_n24_tb(float (&d)[12], uint32_t a0, uint32_t a1, uint32_t a2, uint32_t a3, uint64_t db, int scale_d) {
    asm volatile("{\n.reg .pred p;\nsetp.ne.b32 p, %17, 0;\n"
        "wgmma.mma_async.sync.aligned.m64n24k16.f32.bf16.bf16 "
        "{%0, %1, %2, %3, %4, %5, %6, %7, %8, %9, %10, %11}, "
        "{%12, %13, %14, %15}, %16, p, 1, 1, 1;\n}\n"
        : "+f"(d[0]), "+f"(d[1]), "+f"(d[2]), "+f"(d[3]), "+f"(d[4]), "+f"(d[5]), "+f"(d[6]), "+f"(d[7]),
          "+f"(d[8]), "+f"(d[9]), "+f"(d[10]), "+f"(d[11])
        : "r"(a0), "r"(a1), "r"(a2), "r"(a3), "l"(db), "r"(scale_d));
}

constexpr int SEQ = 2048, DM = 640, FF = 1536;
constexpr uint32_t OFF_A = 122880;
constexpr uint32_t OFF_X = 188416;
constexpr uint32_t OFF_S = 229376;
constexpr uint32_t OFF_CSQ = OFF_S + 512;
constexpr uint32_t OFF_V1 = OFF_S + 1472;
constexpr uint32_t SMEM_BYTES = 232448;
constexpr uint32_t QSTAGE = 30720, BSLOT = 24576;
constexpr uint32_t KVP = 11264, KVH = 2 * KVP;
constexpr uint32_t OFF_KV = 55296;
constexpr uint32_t OREC = 10240, HREC = 10752;
enum { B_QFULL = 0, B_QEMPTY = 4, B_BFULL = 8, B_BEMPTY = 13, B_AFULL = 18, B_AEMPTY = 26, B_STG = 34, B_KVFULL = 36,
       B_KV0 = 40, B_QKVDONE = 41, B_ATT = 42, B_XFREE = 45, B_RECV = 46, B_VECQ = 48, B_VEC1 = 49, B_SLAB = 50, B_GO = 52,
       B_KVOUT = 53, B_XSLAB = 55, B_D1 = 56, B_H1T = 57, B_KST = 61, B_PRD = 62, B_COUNT = 64 };
enum { F_KV = 0, F_O = 256, F_H = 512, F_H1 = 768, F_COUNT = 1024 };
#define KSPLIT 1
enum { B_KIN = B_QFULL + 3 };

#define HSTG 1
#define PART_BF16 1
constexpr uint32_t RECV_BYTES = PART_BF16 ? 10240 : 20480;

struct Params {
    CUtensorMap mX, mWq, mWqC, mWqS, mW1S, mWo, mWoH, mWoT, mWoTH, mW1, mW2, mW2H, mOut, mOutT;
    const __nv_bfloat16 *x, *wo, *b1, *w2, *b2;
};

__device__ __align__(1024) uint8_t g_kv[32 * 8 * KVH];
__device__ __align__(1024) uint8_t g_o[32 * 8 * OREC];
__device__ __align__(1024) uint8_t g_h[32 * 8 * HREC];
__device__ __align__(1024) uint8_t g_h1[32 * 24 * 8192];
__device__ __align__(128) unsigned long long g_csq[8 * 240];
__device__ __align__(128) unsigned long long g_cs1[8 * 192];
__device__ __align__(128) unsigned g_flags[F_COUNT];
__device__ unsigned g_done;
#define TS2(i)
#define TS(i)
#define TSW(i)
#define TS1(i)

__device__ __forceinline__ uint32_t smem_u32(const void* p) { return (uint32_t)__cvta_generic_to_shared(p); }
__device__ __forceinline__ void mbar_init(uint32_t bar, int cnt) { asm volatile("mbarrier.init.shared::cta.b64 [%0], %1;" :: "r"(bar), "r"(cnt) : "memory"); }
__device__ __forceinline__ void mbar_expect_tx(uint32_t bar, uint32_t bytes) { asm volatile("mbarrier.arrive.expect_tx.shared::cta.b64 _, [%0], %1;" :: "r"(bar), "r"(bytes) : "memory"); }
__device__ __forceinline__ void mbar_arrive(uint32_t bar) { asm volatile("mbarrier.arrive.shared::cta.b64 _, [%0];" :: "r"(bar) : "memory"); }
__device__ __forceinline__ uint32_t mapa(uint32_t a, uint32_t cta) { uint32_t r; asm("mapa.shared::cluster.u32 %0, %1, %2;" : "=r"(r) : "r"(a), "r"(cta)); return r; }
constexpr uint32_t WAIT_LIMIT = 400000000u;
constexpr uint32_t TRY_LIMIT = 20000u;
__device__ __forceinline__ void mbar_wait_spin(uint32_t bar, uint32_t parity) {
    asm volatile("{\n.reg .pred p;\n.reg .u32 t0, t1;\n"
                 "mbarrier.try_wait.parity.shared::cta.b64 p, [%0], %1;\n@p bra DONE;\n"
                 "mov.u32 t0, %%clock;\n"
                 "LOOP:\nmbarrier.try_wait.parity.shared::cta.b64 p, [%0], %1;\n@p bra DONE;\n"
                 "mov.u32 t1, %%clock;\nsub.u32 t1, t1, t0;\nsetp.lt.u32 p, t1, %2;\n@p bra LOOP;\ntrap;\n"
                 "DONE:\n}" :: "r"(bar), "r"(parity), "n"(WAIT_LIMIT) : "memory");
}
__device__ __forceinline__ void mbar_wait_ft(uint32_t bar, uint32_t parity) {
    asm volatile("{\n.reg .pred p, q;\n.reg .u32 c;\nmov.u32 c, 0;\n"
                 "LOOP:\nmbarrier.try_wait.parity.shared::cta.b64 p, [%0], %1;\n"
                 "add.u32 c, c, 1;\nsetp.lt.and.u32 q, c, %2, !p;\n@q bra LOOP;\n}" :: "r"(bar), "r"(parity), "n"(1000000) : "memory");
}
__device__ __forceinline__ void mbar_wait_sleep(uint32_t bar, uint32_t parity) {
    asm volatile("{\n.reg .pred p, q;\n.reg .u32 c;\nmov.u32 c, 0;\n"
                 "LOOP:\nmbarrier.try_wait.parity.shared::cta.b64 p, [%0], %1, 100000;\n"
                 "add.u32 c, c, 1;\nsetp.lt.and.u32 q, c, %2, !p;\n@q bra LOOP;\n}" :: "r"(bar), "r"(parity), "n"(TRY_LIMIT) : "memory");
}
#define PUSHAT 1
#define WM 7
template <int CLS> __device__ __forceinline__ void mbar_wait(uint32_t bar, uint32_t parity) {
#define WFT 0
    if (WM & CLS) mbar_wait_sleep(bar, parity); else if (WFT & CLS) mbar_wait_ft(bar, parity); else mbar_wait_spin(bar, parity);
}
__device__ __forceinline__ void mbar_arrive_if(uint32_t bar, bool on) {
    asm volatile("{\n.reg .pred p;\nsetp.ne.u32 p, %1, 0;\n@p mbarrier.arrive.shared::cta.b64 _, [%0];\n}" :: "r"(bar), "r"((uint32_t)on) : "memory");
}
__device__ __forceinline__ void mbar_arrive_remote_if(uint32_t rbar, bool on) {
    asm volatile("{\n.reg .pred p;\nsetp.ne.u32 p, %1, 0;\n@p mbarrier.arrive.shared::cluster.b64 _, [%0];\n}" :: "r"(rbar), "r"((uint32_t)on) : "memory");
}
__device__ __forceinline__ unsigned ld_relaxed(const unsigned* p) { unsigned v; asm volatile("ld.relaxed.gpu.global.u32 %0, [%1];" : "=r"(v) : "l"(p) : "memory"); return v; }
__device__ __forceinline__ void st_relaxed(unsigned* p, unsigned v) { asm volatile("st.relaxed.gpu.global.u32 [%0], %1;" :: "l"(p), "r"(v) : "memory"); }
__device__ __forceinline__ unsigned long long ld_relaxed64(const unsigned long long* p) { unsigned long long v; asm volatile("ld.relaxed.gpu.global.u64 %0, [%1];" : "=l"(v) : "l"(p) : "memory"); return v; }
__device__ __forceinline__ void st_relaxed64(unsigned long long* p, unsigned long long v) { asm volatile("st.relaxed.gpu.global.u64 [%0], %1;" :: "l"(p), "l"(v) : "memory"); }
__device__ __forceinline__ void fence_async_global() { asm volatile("fence.proxy.async.global;" ::: "memory"); }
__device__ __forceinline__ void fence_gpu() { asm volatile("fence.release.gpu;" ::: "memory"); }
__device__ __forceinline__ bool elect_one() {
    uint32_t pred = 0, lid = 0;
    asm volatile("{\n.reg .b32 rx;\n.reg .pred px;\nelect.sync rx|px, %2;\n@px mov.s32 %1, 1;\nmov.s32 %0, rx;\n}" : "+r"(lid), "+r"(pred) : "r"(0xffffffffu));
    return pred != 0;
}
__device__ __forceinline__ int opaque(int v) { asm volatile("" : "+r"(v)); return v; }
__device__ __forceinline__ void fence_async_smem() { asm volatile("fence.proxy.async.shared::cta;" ::: "memory"); }
__device__ __forceinline__ unsigned poll_flags(const unsigned* flags, unsigned need, unsigned valid, unsigned e1) {
    const int lane = threadIdx.x & 31;
    const uint32_t t0 = (uint32_t)clock();
    unsigned seen;
    while (true) {
        unsigned v = ((valid >> lane) & 1) ? ld_relaxed(flags + lane) : e1 + 1;
        seen = __ballot_sync(0xffffffffu, v == e1);
        if ((seen & need) == need) break;
        if ((uint32_t)clock() - t0 > WAIT_LIMIT) __trap();
    }
    return seen;
}
__device__ __forceinline__ void tma2d(uint32_t dst, const CUtensorMap* m, int x, int y, uint32_t bar) {
    asm volatile("cp.async.bulk.tensor.2d.shared::cluster.global.mbarrier::complete_tx::bytes [%0], [%1, {%3, %4}], [%2];"
        :: "r"(dst), "l"(m), "r"(bar), "r"(x), "r"(y) : "memory");
}
__device__ __forceinline__ void tma3d(uint32_t dst, const CUtensorMap* m, int x, int y, int z, uint32_t bar) {
    asm volatile("cp.async.bulk.tensor.3d.shared::cluster.global.mbarrier::complete_tx::bytes [%0], [%1, {%3, %4, %5}], [%2];"
        :: "r"(dst), "l"(m), "r"(bar), "r"(x), "r"(y), "r"(z) : "memory");
}
__device__ __forceinline__ void tma2d_store(const CUtensorMap* m, int x, int y, uint32_t src) {
    asm volatile("cp.async.bulk.tensor.2d.global.shared::cta.bulk_group [%0, {%2, %3}], [%1];" :: "l"(m), "r"(src), "r"(x), "r"(y) : "memory");
}
__device__ __forceinline__ void bulk_load(uint32_t dst, const void* src, uint32_t bytes, uint32_t bar) {
    asm volatile("cp.async.bulk.shared::cluster.global.mbarrier::complete_tx::bytes [%0], [%1], %2, [%3];" :: "r"(dst), "l"(src), "r"(bytes), "r"(bar) : "memory");
}
__device__ __forceinline__ void kv_import(uint32_t dst, int src, int j, uint32_t fb, unsigned e1, int tsi = -1) {
    const uint32_t t0 = (uint32_t)clock();
    const uint8_t* rec = g_kv + (size_t)(src * 8 + j) * KVH;
    asm volatile("" : "+l"(rec));
    while (ld_relaxed(g_flags + F_KV + src * 8 + j) != e1) { if ((uint32_t)clock() - t0 > WAIT_LIMIT) __trap(); }
    fence_async_global();
    mbar_expect_tx(fb, KVH);
    bulk_load(dst, rec, KVH, fb);
}
__device__ __forceinline__ void bulk_store(void* dst, uint32_t src, uint32_t bytes) {
    asm volatile("cp.async.bulk.global.shared::cta.bulk_group [%0], [%1], %2;" :: "l"(dst), "r"(src), "r"(bytes) : "memory");
}
__device__ __forceinline__ void bulk_push(uint32_t rdst, uint32_t src, uint32_t bytes, uint32_t rbar) {
    asm volatile("cp.async.bulk.shared::cluster.shared::cta.mbarrier::complete_tx::bytes [%0], [%1], %2, [%3];" :: "r"(rdst), "r"(src), "r"(bytes), "r"(rbar) : "memory");
}
__device__ __forceinline__ void bulk_commit() { asm volatile("cp.async.bulk.commit_group;" ::: "memory"); }
__device__ __forceinline__ void bulk_wait_all() { asm volatile("cp.async.bulk.wait_group 0;" ::: "memory"); }
__device__ __forceinline__ void prefetch_l2(const void* p, uint32_t bytes) { asm volatile("cp.async.bulk.prefetch.L2.global [%0], %1;" :: "l"(p), "r"(bytes) : "memory"); }
__device__ __forceinline__ void prefetch_map(const CUtensorMap* m) { asm volatile("prefetch.tensormap [%0];" :: "l"(m) : "memory"); }
__device__ __forceinline__ void wg_fence() { asm volatile("wgmma.fence.sync.aligned;" ::: "memory"); }
__device__ __forceinline__ void wg_commit() { asm volatile("wgmma.commit_group.sync.aligned;" ::: "memory"); }
template <int N> __device__ __forceinline__ void wg_wait() { asm volatile("wgmma.wait_group.sync.aligned %0;" :: "n"(N) : "memory"); }
template <int N> __device__ __forceinline__ void zero(float (&a)[N]) {
#pragma unroll
    for (int i = 0; i < N; i++) a[i] = 0.f;
}
template <int N> __device__ __forceinline__ void pin(float (&a)[N]) {
#pragma unroll
    for (int i = 0; i < N; i++) asm volatile("" : "+f"(a[i]) :: "memory");
}
template <int N> __device__ __forceinline__ void pin(uint32_t (&a)[N]) {
#pragma unroll
    for (int i = 0; i < N; i++) asm volatile("" : "+r"(a[i]) :: "memory");
}
__device__ __forceinline__ uint64_t mkdesc(uint32_t addr, uint32_t lbo, uint32_t sbo, uint32_t layout) {
    return (uint64_t)((addr & 0x3FFFF) >> 4) | ((uint64_t)(lbo >> 4) << 16) | ((uint64_t)(sbo >> 4) << 32) | ((uint64_t)layout << 62);
}
__device__ __forceinline__ uint32_t pack2(float lo, float hi) { uint32_t r; asm("cvt.rn.bf16x2.f32 %0, %1, %2;" : "=r"(r) : "f"(hi), "f"(lo)); return r; }
__device__ __forceinline__ uint32_t pack2_relu(float lo, float hi) { uint32_t r; asm("cvt.rn.relu.bf16x2.f32 %0, %1, %2;" : "=r"(r) : "f"(hi), "f"(lo)); return r; }
__device__ __forceinline__ uint32_t sq_bf16x2(uint32_t a) { uint32_t r; asm("mul.rn.bf16x2 %0, %1, %1;" : "=r"(r) : "r"(a)); return r; }
__device__ __forceinline__ float bf_lo(uint32_t v) { return __uint_as_float(v << 16); }
__device__ __forceinline__ float bf_hi(uint32_t v) { return __uint_as_float(v & 0xffff0000u); }
__device__ __forceinline__ float ex2(float x) { float y; asm volatile("ex2.approx.ftz.f32 %0, %1;" : "=f"(y) : "f"(x)); return y; }
__device__ __forceinline__ void stsm4(uint32_t addr, uint32_t r0, uint32_t r1, uint32_t r2, uint32_t r3) {
    asm volatile("stmatrix.sync.aligned.m8n8.x4.shared.b16 [%0], {%1, %2, %3, %4};" :: "r"(addr), "r"(r0), "r"(r1), "r"(r2), "r"(r3) : "memory");
}
__device__ __forceinline__ float2 lds_f2(uint32_t a) { float2 v; asm volatile("ld.shared.v2.f32 {%0, %1}, [%2];" : "=f"(v.x), "=f"(v.y) : "r"(a)); return v; }
__device__ __forceinline__ float4 lds_f4(uint32_t a) { float4 v; asm volatile("ld.shared.v4.f32 {%0, %1, %2, %3}, [%4];" : "=f"(v.x), "=f"(v.y), "=f"(v.z), "=f"(v.w) : "r"(a)); return v; }
__device__ __forceinline__ void wg_bar(int id) { asm volatile("bar.sync %0, 128;" :: "r"(id) : "memory"); }
__device__ __forceinline__ bool wg_bar_and(int id, bool v) {
    uint32_t r;
    asm volatile("{\n.reg .pred p, q;\nsetp.ne.u32 q, %2, 0;\nbarrier.cta.red.and.pred p, %1, 128, q;\nselp.u32 %0, 1, 0, p;\n}" : "=r"(r) : "r"(id), "r"((uint32_t)v) : "memory");
    return r != 0;
}

__device__ __forceinline__ uint64_t mkd(uint32_t lo, uint32_t hi) { return ((uint64_t)hi << 32) | lo; }

__device__ __forceinline__ void qk_issue(float (&S)[32], const uint32_t (&Q)[8], uint32_t kv4, int h) {
    const uint32_t lo = kv4 + (((h >> 1) * KVP + ((h & 1) ? 2048 : 0)) >> 4) + (64u << 16);
    wg_fence();
    wgmma_rs_n64(S, Q[0], Q[1], Q[2], Q[3], mkd(lo, 8), 0);
    wgmma_rs_n64(S, Q[4], Q[5], Q[6], Q[7], mkd(lo + 128, 8), 1);
    wg_commit();
}
__device__ __forceinline__ void pv_one(float (&O)[12], const uint32_t (&P)[16], uint32_t kv4, int h, int g) {
    const uint32_t lo = kv4 + (((h >> 1) * KVP + 5120 + ((h & 1) ? 3072 : 0) + g * 256) >> 4) + (8u << 16);
    wgmma_rs_n24_tb(O, P[4 * g], P[4 * g + 1], P[4 * g + 2], P[4 * g + 3], mkd(lo, 64), 1);
}
template <bool WAITV = false>
__device__ __forceinline__ void att_tile(float (&S)[32], uint32_t (&P)[16], float (&O)[12], uint32_t kv4, int h, uint32_t vbar = 0) {
    float e[32];
#pragma unroll
    for (int i = 0; i < 32; i++) e[i] = ex2(S[i]);
#pragma unroll
    for (int i = 0; i < 16; i++) P[i] = pack2(e[2 * i], e[2 * i + 1]);
    if (WAITV) mbar_wait<16>(vbar, 0);
    wg_fence();
#pragma unroll
    for (int g = 0; g < 4; g++) pv_one(O, P, kv4, h, g);
    wg_commit();
}

__device__ __forceinline__ float kv_elem(const uint8_t* kb, int cc, bool isv) {
    const int G = cc >> 3, pt = G >= 5, gl = G - 5 * pt;
    const int slot = !isv ? gl : 5 + (gl < 2 ? gl : gl == 2 ? 2 + ((cc >> 2) & 1) : gl + 1);
    return __uint_as_float((uint32_t)__ldcg(reinterpret_cast<const unsigned short*>(kb + pt * KVP + slot * 1024 + (cc & 7) * 2)) << 16);
}
__device__ __forceinline__ void attn_fallback(uint8_t* ring, int hb, int j, unsigned e1) {
    const int t = threadIdx.x & 127;
#pragma unroll 1
    for (int d = 0; d <= 4; d++) {
        if (hb - d >= 0) poll_flags(g_flags + F_KV + (hb - d) * 8 + j, 1u, 1u, e1);
    }
    const int row = t >> 1, i = hb * 64 + row, j0 = max(0, i - 255);
    __nv_bfloat16* qrow = reinterpret_cast<__nv_bfloat16*>(ring + KVH + row * 160);
    float* sc = reinterpret_cast<float*>(ring) + t * 41;
#pragma unroll 1
    for (int hh = 0; hh < 2; hh++) {
        const int c0 = ((t & 1) * 2 + hh) * 20;
#pragma unroll 1
        for (int d = 0; d < 20; d++) { sc[d] = __bfloat162float(qrow[c0 + d]); sc[20 + d] = 0.f; }
        float m = -INFINITY, l = 0.f;
#pragma unroll 1
        for (int it = j0; it < 2 * i + 2 - j0; it++) {
            const bool second = it > i;
            const int kj = second ? it - (i + 1 - j0) : it;
            const uint8_t* kb = g_kv + (size_t)((kj >> 6) * 8 + j) * KVH + (kj & 63) * 16;
            float s = 0.f;
#pragma unroll 1
            for (int d = 0; d < 20; d++) s += sc[d] * kv_elem(kb, c0 + d, false);
            if (!second) m = fmaxf(m, s);
            else {
                const float pp = exp2f(s - m);
                l += pp;
#pragma unroll 1
                for (int d = 0; d < 20; d++) sc[20 + d] += pp * kv_elem(kb, c0 + d, true);
            }
        }
#pragma unroll 1
        for (int d = 0; d < 20; d++) qrow[c0 + d] = __float2bfloat16(sc[20 + d] / l);
    }
    wg_bar(1 + (threadIdx.x >> 7));
#pragma unroll 1
    for (int d = 0; d < 40; d++) {
        const int c = (t & 1) * 40 + d;
        const int off = c < 64 ? row * 128 + (((c >> 3) ^ (row & 7)) << 4) : 8192 + ((c - 64) >> 3) * 1024 + row * 16;
        *reinterpret_cast<__nv_bfloat16*>(ring + off + (c & 7) * 2) = qrow[c];
    }
}
#define XSWAP 1
__device__ __forceinline__ uint32_t kv_slot(int d) {
    if (XSWAP == 2) return d == 4 ? OFF_X : OFF_KV + (d == 1 ? 0 : 4 - d) * KVH;
    return d == (XSWAP ? 2 : 4) ? OFF_X : OFF_KV + (XSWAP && d == 4 ? 1 : d - 1) * KVH;
}
__device__ __forceinline__ int ord(int t, int own) { return t == 0 ? own : (t - 1 < own ? t - 1 : t); }
__device__ __forceinline__ int ord2(int t, int own) { return t < 2 ? own ^ t : (t - 2 < (own & 6) ? t - 2 : t); }

__global__ void __cluster_dims__(2, 1, 1) __launch_bounds__(384, 1) fused_block_kernel(const __grid_constant__ Params P) {
    extern __shared__ __align__(1024) uint8_t smem[];
    const uint32_t sb = smem_u32(smem);
    const int tid = threadIdx.x, lane = tid & 31;
#define PFT 0
    if (tid == PFT) { prefetch_map(&P.mX); prefetch_map(&P.mWq); prefetch_map(&P.mWqC); }
    const int warp = __shfl_sync(0xffffffffu, tid >> 5, 0);
    const int c_ = blockIdx.x >> 1, p = blockIdx.x & 1;
    int u_;
    asm("{\n.reg .pred p, q;\n.reg .b32 a;\nsetp.lt.u32 p, %1, 4;\nsetp.lt.u32 q, %1, 36;\nselp.b32 a, %3, %4, q;\nselp.b32 %0, %2, a, p;\n}"
        : "=r"(u_) : "r"(c_), "r"(32 + 8 * c_), "r"(c_ - 4), "r"(c_ - 3 + ((c_ * 37 - 36 * 37) >> 8)));
    const int r = ((u_ & 4) << 1) + (u_ >> 3), jp = u_ & 3;
    const int b = r * 8 + jp * 2 + p;
    const int j = jp + 4 * p;
    const int cown = 2 * jp + p;
    auto bar = [&](int i) -> uint32_t { return sb + OFF_S + 8 * i; };

    auto qkv_stage = [&](int k) {
        const int s = k & 3;
        const uint32_t fb = bar(B_QFULL + s), st = sb + s * QSTAGE;
        mbar_expect_tx(fb, 16384 + QSTAGE);
        tma2d(sb + OFF_A + s * 8192, &P.mX, k * 64, r * 128, fb);
        tma3d(st, &P.mWq, 80 * j, k * 64, 0, fb);
        tma2d(sb + OFF_A + 32768 + s * 8192, &P.mX, k * 64, r * 128 + 64, fb);
        tma3d(st + 24576, &P.mWqC, 80 * j + 64, k * 64, 0, fb);
    };
    if (warp == 8) {
        if (elect_one()) {
            for (int i = 0; i < 4; i++) mbar_init(bar(B_QFULL + i), 1);
            asm volatile("fence.mbarrier_init.release.cluster;" ::: "memory");
            qkv_stage(0);
        }
        __syncwarp();
        asm volatile("bar.arrive 0, 384;" ::: "memory");
        asm volatile("barrier.cluster.arrive.relaxed.aligned;" ::: "memory");
    }
    if (warp == 9) {
        if (elect_one()) {
            for (int i = 0; i < 4; i++) mbar_init(bar(B_QEMPTY + i), 8);
            for (int i = 0; i < 5; i++) { mbar_init(bar(B_BFULL + i), 1); mbar_init(bar(B_BEMPTY + i), 2); }
            for (int i = 0; i < 8; i++) { mbar_init(bar(B_AFULL + i), 1); mbar_init(bar(B_AEMPTY + i), 1); }
            for (int i = 0; i < 2; i++) { mbar_init(bar(B_STG + i), 128); mbar_init(bar(B_RECV + i), 1); mbar_init(bar(B_SLAB + i), 1); mbar_init(bar(B_KVOUT + i), 1);
                                          mbar_init(bar(B_H1T + i), 128); mbar_init(bar(B_H1T + 2 + i), 128); }
            for (int i = 0; i < 4; i++) mbar_init(bar(B_KVFULL + i), 1);
            for (int i = 0; i < 3; i++) mbar_init(bar(B_ATT + i), 8);
            mbar_init(bar(B_KV0), 1); mbar_init(bar(B_QKVDONE), 2); mbar_init(bar(B_XFREE), XSWAP == 1 ? 8 : 4);
            mbar_init(bar(B_VECQ), 1); mbar_init(bar(B_VEC1), 1); mbar_init(bar(B_XSLAB), 1); mbar_init(bar(B_D1), 1);
            mbar_init(bar(B_GO), 1);
            mbar_init(bar(B_KST), 128);
            mbar_init(bar(B_PRD), 1); mbar_init(bar(B_PRD + 1), 1);
            asm volatile("fence.mbarrier_init.release.cluster;" ::: "memory");
            fence_async_smem();
        }
        __syncwarp();
        asm volatile("bar.arrive 3, 64;" ::: "memory");
    }

    if (warp >= 8) asm volatile("setmaxnreg.dec.sync.aligned.u32 56;");
    if (warp == 8) {
        if (elect_one()) {
#pragma unroll 1
            for (int k = 1; k < 4; k++) qkv_stage(k);
        }
        __syncwarp();
    }
    if (warp >= 8) {
        if (warp == 8) {
            asm volatile("bar.sync 3, 64;" ::: "memory");
            if (elect_one()) {
#pragma unroll 1
                for (int k = 4; k < 10; k++) { mbar_wait<2>(bar(B_QEMPTY + (k & 3)), ((k >> 2) - 1) & 1); qkv_stage(k); }
                TS1(2);
                const unsigned e1 = (ld_relaxed(&g_done) >> 7) + 1;
                mbar_wait<4>(bar(B_QKVDONE), 0);
#pragma unroll 1
                for (int i = 1; i <= 4; i++) {
#define IMPORD 1
#define D1AT 2
                    const int d = IMPORD ? i ^ (i >> 1 & 1) : i;
                    if (d == (XSWAP == 1 ? 2 : 4)) mbar_wait<4>(bar(B_XSLAB), 0);
                    if (KSPLIT && d == 1) {
                        if (r > 0) {
                            const uint8_t* rec = g_kv + (size_t)((2 * r - 1) * 8 + j) * KVH;
                            const unsigned* fl = g_flags + F_KV + (2 * r - 1) * 8 + j;
                            const uint32_t dst = sb + kv_slot(1), kb = bar(B_KIN), vb = bar(B_KVFULL), t0 = (uint32_t)clock();
                            mbar_expect_tx(kb, 10240); mbar_expect_tx(vb, 12288);
                            asm volatile("" : "+l"(rec));
                            while (ld_relaxed(fl) != e1) { if ((uint32_t)clock() - t0 > WAIT_LIMIT) __trap(); }
                            TS1(6);
                            fence_async_global();
                            bulk_load(dst, rec, 5120, kb);
                            bulk_load(dst + KVP, rec + KVP, 5120, kb);
                            bulk_load(dst + 5120, rec + 5120, 6144, vb);
                            bulk_load(dst + KVP + 5120, rec + KVP + 5120, 6144, vb);
                            TS1(14);
                        }
                    } else if (2 * r - d >= 0) kv_import(sb + kv_slot(d), 2 * r - d, j, bar(B_KVFULL + d - 1), e1, d);
                    if (i == D1AT) mbar_arrive(bar(B_D1));
                }
                TS1(7);
                int s = 0; uint32_t ph = 1;
#pragma unroll 1
                for (int n = 0; n < 27; n++) {
                    if (n < 5) mbar_wait<2>(bar(n < 2 ? B_QKVDONE : B_ATT + n - 2), 0);
                    else mbar_wait<2>(bar(B_BEMPTY + s), ph);
                    const uint32_t fb = bar(B_BFULL + s), st = sb + s * BSLOT;
                    if (n >= 5 && n < 15) {
                        const int u = n - 5, k = u < 8 ? 64 * ord2(u, cown) : 64 * u;
                        mbar_expect_tx(fb, 24576);
                        tma2d(st, &P.mW1, 192 * j, k, fb);
                        tma2d(st + 8192, &P.mW1, 192 * j + 64, k, fb);
                        tma2d(st + 16384, &P.mW1, 192 * j + 128, k, fb);
                    } else {
                        mbar_expect_tx(fb, 20480);
                        if (n == 4) {
                            tma3d(st, &P.mWoT, 64 * cown, 64, 4 * p, fb);
                            tma3d(st + 8192, &P.mWoT, 64 * (cown ^ 1), 64, 4 * p, fb);
                            tma3d(st + 16384, &P.mWoTH, 512 + 32 * jp, 64, 4 * p, fb);
                        } else {
                            const bool wo = n < 5;
                            const int v = n - 15, g3 = v / 3;
                            const int k = wo ? 80 * (4 * p + ord(n, jp)) : 768 * p + 192 * ord(g3, jp) + 64 * (v - 3 * g3);
                            const CUtensorMap* m0 = wo ? &P.mWo : &P.mW2;
                            const CUtensorMap* m1 = wo ? &P.mWoH : &P.mW2H;
                            tma2d(st, m0, 64 * cown, k, fb);
                            tma2d(st + 8192, m0, 64 * (cown ^ 1), k, fb);
                            tma2d(st + 16384, m1, 512 + 32 * jp, k, fb);
                        }
                    }
                    if (++s == 5) { s = 0; ph ^= 1; }
                }
                TS1(3);
            }
            __syncwarp();
            asm volatile("barrier.cluster.wait.aligned;" ::: "memory");
        } else if (warp == 11) {
            asm volatile("bar.sync 0, 384;" ::: "memory");
            asm volatile("barrier.cluster.arrive.relaxed.aligned;" ::: "memory");
            const unsigned e1 = (ld_relaxed(&g_done) >> 7) + 1;
            if (elect_one()) {
                prefetch_map(&P.mWqS); prefetch_map(&P.mW1S);
                if (r < 15) {
                    mbar_expect_tx(bar(B_SLAB), 20480);
#pragma unroll 1
                    for (int i = 0; i < 5; i++) tma2d(sb + OFF_X + i * 4096, &P.mWqS, (r / 5) * 640 + 80 * j + 16 * (r % 5), 128 * i, bar(B_SLAB));
                }
                prefetch_map(&P.mWo); prefetch_map(&P.mWoH); prefetch_map(&P.mWoT); prefetch_map(&P.mWoTH); prefetch_map(&P.mW1);
                prefetch_map(&P.mW2); prefetch_map(&P.mW2H); prefetch_map(&P.mOut); prefetch_map(&P.mOutT);
            }
            __syncwarp();
#pragma unroll 1
            for (int job = 0; job < 2; job++) {
                if (r < (job ? 12 : 15)) {
                    mbar_wait<2>(bar(B_SLAB + job), 0);
                    float a[8];
#pragma unroll
                    for (int i = 0; i < 8; i++) a[i] = 0.f;
                    const uint32_t src = sb + OFF_X + job * 20480 + lane * 16;
#pragma unroll 4
                    for (int i = 0; i < 40; i++) {
                        uint4 v; asm volatile("ld.shared.v4.b32 {%0, %1, %2, %3}, [%4];" : "=r"(v.x), "=r"(v.y), "=r"(v.z), "=r"(v.w) : "r"(src + i * 512));
                        a[0] += bf_lo(v.x); a[1] += bf_hi(v.x); a[2] += bf_lo(v.y); a[3] += bf_hi(v.y);
                        a[4] += bf_lo(v.z); a[5] += bf_hi(v.z); a[6] += bf_lo(v.w); a[7] += bf_hi(v.w);
                    }
                    float mine = 0.f;
#pragma unroll
                    for (int i = 0; i < 8; i++) {
#pragma unroll
                        for (int o = 2; o < 32; o <<= 1) a[i] += __shfl_xor_sync(0xffffffffu, a[i], o);
                        const float v = __shfl_sync(0xffffffffu, a[i], lane >> 3);
                        if ((lane & 7) == i) mine = v;
                    }
                    unsigned long long* dst = job ? g_cs1 + j * 192 + 16 * r : g_csq + j * 240 + (r / 5) * 80 + 16 * (r % 5);
                    if (lane < 16) st_relaxed64(dst + lane, ((unsigned long long)e1 << 32) | __float_as_uint(mine));
                }
                if (job == 0 && r < 12 && elect_one()) {
                    mbar_expect_tx(bar(B_SLAB + 1), 20480);
#pragma unroll 1
                    for (int i = 0; i < 5; i++) tma2d(sb + OFF_X + 20480 + i * 4096, &P.mW1S, 192 * j + 16 * r, 128 * i, bar(B_SLAB + 1));
                }
                __syncwarp();
                if (job == 1 && lane == 0) mbar_arrive(bar(B_XSLAB));
                const int n = job ? 192 : 240;
                const unsigned long long* src = job ? g_cs1 + j * 192 : g_csq + j * 240;
                float* dst = reinterpret_cast<float*>(smem + (job ? OFF_V1 : OFF_CSQ));
                const uint32_t t0 = (uint32_t)clock();
                while (true) {
                    unsigned long long v[8];
                    bool ok = true;
#pragma unroll
                    for (int m = 0; m < 8; m++) { const int i = lane + 32 * m; v[m] = i < n ? ld_relaxed64(src + i) : (unsigned long long)e1 << 32; }
#pragma unroll
                    for (int m = 0; m < 8; m++) {
                        const int i = lane + 32 * m;
                        ok = ok && (unsigned)(v[m] >> 32) == e1;
                        if (i < n) dst[job ? 4 * (i >> 1) + (i & 1) : i] = __uint_as_float((unsigned)v[m]);
                    }
                    if (__all_sync(0xffffffffu, ok)) break;
                    if ((uint32_t)clock() - t0 > WAIT_LIMIT) __trap();
                }
                if (job) {
#pragma unroll 1
                    for (int i = lane; i < 96; i += 32) {
                        const uint32_t bb = __ldg(reinterpret_cast<const uint32_t*>(P.b1 + 192 * j + 2 * i));
                        *reinterpret_cast<float2*>(dst + 4 * i + 2) = make_float2(bf_lo(bb), bf_hi(bb));
                    }
                }
                __syncwarp();
                if (lane == 0) mbar_arrive(bar(B_VECQ + job));
                TS(4 + job);
                if (job == 0 && elect_one()) {
                    prefetch_l2(reinterpret_cast<const uint8_t*>(P.wo) + b * 6400, 6400);
                    prefetch_l2(reinterpret_cast<const uint8_t*>(P.w2) + b * 15360, 15360);
                }
            }
            asm volatile("barrier.cluster.wait.aligned;" ::: "memory");
        } else {
            const int w = warp - 9, hb = 2 * r + w;
            asm volatile("bar.sync 0, 384;" ::: "memory");
            asm volatile("barrier.cluster.arrive.relaxed.aligned;" ::: "memory");
            const unsigned e1 = (ld_relaxed(&g_done) >> 7) + 1;
            asm volatile("barrier.cluster.wait.aligned;" ::: "memory");
            const uint32_t aring = sb + OFF_A + w * 32768, stg = bar(B_STG + w);
            if (elect_one()) {
                uint8_t* gdst = g_kv + (size_t)(hb * 8 + j) * KVH;
                if (w == 1) {
                    mbar_wait<4>(bar(B_KST), 0);
                    bulk_store(gdst, aring, 5120); bulk_store(gdst + KVP, aring + KVP, 5120);
                    mbar_wait<4>(stg, 0);
                    TS1(87);
                    bulk_store(gdst + 5120, aring + 5120, 6144); bulk_store(gdst + KVP + 5120, aring + KVP + 5120, 6144);
                } else {
                    mbar_wait<4>(stg, 0);
                    mbar_wait<4>(bar(B_KVOUT + 1), 0);
                    mbar_wait<4>(bar(B_D1), 0);
                    TS1(84);
                    bulk_store(gdst, aring, KVH);
                }
                bulk_commit(); bulk_wait_all();
                TS1(85 + 3 * w);
                fence_gpu();
#define KVRED 0
                if (KVRED) asm volatile("red.relaxed.gpu.global.max.u32 [%0], %1;" :: "l"(g_flags + F_KV + hb * 8 + j), "r"(e1) : "memory");
                else st_relaxed(g_flags + F_KV + hb * 8 + j, e1);
                TS1(86 + 3 * w);
                mbar_arrive(bar(B_KVOUT + w));
            }
            __syncwarp();
            if (elect_one()) {
                uint32_t seq_h = 0;
#pragma unroll
                for (int i = 0; i < 6; i++) seq_h |= (uint32_t)ord2(i + 2, cown) << (3 * i);
                const uint32_t fullb = bar(B_AFULL + w * 4);
                uint32_t par = 0xf;
                const uint32_t stale = (e1 & 1) ? 0u : ~0u;
#pragma unroll 1
                for (int ph = 0; ph < 3; ph++) {
                    const uint8_t* gsrc = ph == 0 ? g_o + (size_t)hb * 8 * OREC : ph == 1 ? g_h + (size_t)hb * 8 * HREC : g_h1 + (size_t)hb * 24 * 8192;
                    const uint32_t rec = ph == 0 ? OREC : ph == 1 ? HREC : 24576;
                    unsigned* fla = g_flags + F_O + ph * 256 + hb * 8;
                    {
                        uint8_t* gdst = const_cast<uint8_t*>(gsrc) + (ph == 1 ? cown : j) * rec;
                        uint32_t done = 0;
                        if (ph == 2) {
#pragma unroll 1
                            for (; done < 16384; done += 8192) {
                                mbar_wait<4>(bar(B_H1T + (done >> 12) + w), 0);
                                bulk_store(gdst + done, aring + done, 8192);
                            }
                        }
                        mbar_wait<4>(stg, (ph + 1) & 1);
                        TS1(100 + w * 9 + ph * 3);
                        if (ph == 1) {
                            bulk_store(gdst, aring, 8192);
                            bulk_store(gdst + 8192, aring + 24576, HSTG ? 2048 : HREC - 8192);
                        } else bulk_store(gdst + done, aring + done, rec - done);
                        bulk_commit();
                    }
                    const uint32_t f1 = 4 * p + ord(1, jp), f2 = 4 * p + ord(2, jp), f3 = 4 * p + ord(3, jp);
                    uint32_t seen = 0, off = 0, seq = ph == 0 ? f1 | f2 << 3 | f3 << 6 : ph == 1 ? seq_h : f1 * 0111u | f2 * 0111000u | f3 * 0111000000u;
                    par ^= (2u << ph) - 1;
                    bulk_wait_all();
                    TS1(101 + w * 9 + ph * 3);
                    if (ph == 1) bulk_push(mapa(aring + 8192, p ^ 1), aring, 8192, mapa(fullb + 8, p ^ 1));
                    if (HSTG && ph == 1) mbar_wait_spin(bar(w ? B_GO : B_D1), w ^ 1);
#define MERGEF 1
                    if (MERGEF && ph == 2 && w == 1) mbar_arrive(bar(B_GO));
                    else {
                        if (MERGEF && ph == 2) mbar_wait_spin(bar(B_GO), HSTG);
                        fence_gpu();
                        asm volatile("red.relaxed.gpu.global.xor.b32 [%0], %1;" :: "l"(fla), "r"(1u << (ph == 1 ? cown : j)) : "memory");
                        if (MERGEF && ph == 2) asm volatile("red.relaxed.gpu.global.xor.b32 [%0], %1;" :: "l"(fla + 8), "r"(1u << j) : "memory");
                    }
                    TS1(102 + w * 9 + ph * 3);
                    if (ph == 1) { mbar_wait<4>(fullb + 8, 1); mbar_arrive_remote_if(mapa(bar(B_PRD + w), p ^ 1), true); }
                    auto await = [&](uint32_t need) {
                        const uint32_t t0 = (uint32_t)clock();
                        do {
                            seen = ld_relaxed(fla) ^ stale;
                            if ((uint32_t)clock() - t0 > WAIT_LIMIT) __trap();
                        } while ((seen & need) != need);
                        fence_async_global();
                    };
                    int t = ph + 1;
#pragma unroll 1
                    do {
                        const uint32_t f = seq & 7;
                        seq >>= 3;
                        if (!((seen >> f) & 1) || t + 8 * ph == 12) {
                            if (t + 8 * ph == 12) mbar_wait_spin(bar(B_PRD + w), 0);
                            if (!((seen >> f) & 1)) {
                                await(1u << f);
                            }
                        }
                        const uint32_t s = t & 3, fb = fullb + 8 * s;
                        mbar_wait_spin(fb + 64, (par >> s) & 1);
                        par ^= 1u << s;
                        mbar_expect_tx(fb, 8192);
                        bulk_load(aring + s * 8192, gsrc + f * rec + off, 8192, fb);
                        off = ph == 2 && off < 16384 ? off + 8192 : 0;
                    } while (++t < 4 * ph + 4);
#pragma unroll 1
                    for (; t < (ph == 0 ? 5 : ph == 1 ? 10 : 0); t++) {
                        const uint32_t first = ph == 0 ? 4 * p : 4 * (t - 8), s = t & 3, fb = fullb + 8 * s;
                        const uint32_t need = ph == 1 ? 0xffu : 15u << first;
                        if ((seen & need) != need) await(need);
                        mbar_wait_spin(fb + 64, (par >> s) & 1);
                        par ^= 1u << s;
                        mbar_expect_tx(fb, 8192);
#pragma unroll 1
                        for (int i = 0; i < 4; i++) bulk_load(aring + s * 8192 + i * 2048, gsrc + (first + i) * rec + 8192, 2048, fb);
                    }
                    if (ph == 0) { mbar_wait<4>(fullb + 8, 0); mbar_expect_tx(fullb + 8, 8192); }
                    TS1(8 + ph + w * 8);
                }
                mbar_wait<4>(stg, 0);
                tma2d_store(&P.mOut, 64 * cown, hb * 64, aring);
                tma2d_store(&P.mOutT, 512 + 16 * cown, hb * 64, aring + 8192);
                bulk_commit(); bulk_wait_all();
                if (w == 0) atomicAdd(&g_done, 1u);
            }
            __syncwarp();
            TS(12 + w * 8);
        }
    } else {
        asm volatile("bar.sync 0, 384;" ::: "memory");
        asm volatile("barrier.cluster.arrive.relaxed.aligned;" ::: "memory");
        asm volatile("setmaxnreg.inc.sync.aligned.u32 224;");
        const int w = warp >> 2, t = tid & 127, wq = warp & 3, q = lane & 3, g8 = lane >> 2;
        const int hb = 2 * r + w;
        const uint32_t aring = sb + OFF_A + w * 32768;

        uint32_t Q[4][8];
        {
            float acc[96], acc2[24];
            zero(acc); zero(acc2);
            float sx = 0.f, sxx = 0.f;
            const uint32_t xrow = aring + (t >> 1) * 128, xsw = ((t >> 1) & 7) ^ ((t & 1) * 4);
#pragma unroll 1
            for (int k = 0; k < 10; k++) {
                const int s = k & 3;
                mbar_wait<1>(bar(B_QFULL + s), (k >> 2) & 1);
                TSW(64 + w * 10 + k);
                const uint64_t da = mkdesc(aring + s * 8192, 16, 1024, 1);
                const uint64_t db = mkdesc(sb + s * QSTAGE, 8192, 1024, 1), dc = mkdesc(sb + s * QSTAGE + 24576, 2048, 256, 3);
                wg_fence();
#pragma unroll
                for (int kk = 0; kk < 4; kk++) {
                    wgmma_ss_n192_tb(acc, da + 2 * kk, db + 128 * kk, 1);
                    wgmma_ss_n48_tb(acc2, da + 2 * kk, dc + 32 * kk, 1);
                }
                wg_commit();
#pragma unroll
                for (int i = 0; i < 4; i++) {
                    uint4 v; asm volatile("ld.shared.v4.b32 {%0, %1, %2, %3}, [%4];" : "=r"(v.x), "=r"(v.y), "=r"(v.z), "=r"(v.w) : "r"(xrow + s * 8192 + ((xsw ^ i) << 4)));
                    const uint32_t u[4] = {v.x, v.y, v.z, v.w};
#pragma unroll
                    for (int e = 0; e < 4; e++) { const float a = bf_lo(u[e]), c = bf_hi(u[e]); sx += a + c; sxx = fmaf(a, a, fmaf(c, c, sxx)); }
                }
                wg_wait<1>();
                if (lane == 0 && k > 0) mbar_arrive(bar(B_QEMPTY + ((k - 1) & 3)));
            }
            sx += __shfl_xor_sync(0xffffffffu, sx, 1); sxx += __shfl_xor_sync(0xffffffffu, sxx, 1);
            const float mean = sx * (1.f / DM), rstd = rsqrtf(fmaxf(sxx * (1.f / DM) - mean * mean, 0.f) + 1e-5f), nm = -mean * rstd;
            const float r0 = __shfl_sync(0xffffffffu, rstd, 2 * g8), r1 = __shfl_sync(0xffffffffu, rstd, 2 * g8 + 16);
            const float n0 = __shfl_sync(0xffffffffu, nm, 2 * g8), n1 = __shfl_sync(0xffffffffu, nm, 2 * g8 + 16);
            mbar_wait<8>(bar(B_VECQ), 0);
            wg_wait<0>();
            pin(acc); pin(acc2);
            if (t == 0) mbar_arrive(bar(B_QKVDONE));
            TSW(25 + w * 16);
            mbar_wait<8>(bar(w ? B_VECQ : B_STG + 1), 0);
            const uint32_t kvw = aring + (wq * 16 + ((lane >> 3) & 1) * 8 + (lane & 7)) * 16;
            const bool second = lane >= 16, lo = q < 2;
            uint32_t vv[10][2];
#pragma unroll
            for (int sec = 0; sec < 2; sec++) {
#pragma unroll
                for (int GG = 0; GG < 10; GG++) {
                    const float* a = GG < 8 ? &acc[32 * (sec + 1) + 4 * GG] : &acc2[8 * (sec + 1) + 4 * (GG - 8)];
                    const float2 cs = lds_f2(sb + OFF_CSQ + ((sec + 1) * 80 + 8 * GG + 2 * q) * 4);
                    vv[GG][0] = pack2(fmaf(r0, a[0], n0 * cs.x), fmaf(r0, a[1], n0 * cs.y));
                    vv[GG][1] = pack2(fmaf(r1, a[2], n1 * cs.x), fmaf(r1, a[3], n1 * cs.y));
                }
                if (sec == 0) {
#pragma unroll
                    for (int G = 0; G < 10; G += 2) {
                        const uint32_t o1 = (G / 5) * KVP + (G % 5) * 1024, o2 = ((G + 1) / 5) * KVP + ((G + 1) % 5) * 1024;
                        stsm4(kvw + (second ? o2 : o1), vv[G][0], vv[G][1], vv[G + 1][0], vv[G + 1][1]);
                    }
                    asm volatile("{\n.reg .pred p;\nsetp.ne.u32 p, %1, 0;\n@p fence.proxy.async.shared::cta;\n@p mbarrier.arrive.shared::cta.b64 _, [%0];\n}" :: "r"(bar(B_KST)), "r"(w) : "memory");
                } else {
                    const uint32_t one_a = q == 2 ? 0x3f80u : 0u, one_b = q == 0 ? 0x3f80u : 0u, vw = kvw + 5120 + (second ? 1024 : 0);
#pragma unroll
                    for (int pt = 0; pt < 2; pt++) {
                        const int G = 5 * pt;
                        stsm4(vw + pt * KVP, vv[G][0], vv[G][1], vv[G + 1][0], vv[G + 1][1]);
                        stsm4(vw + pt * KVP + 2048, lo ? vv[G + 2][0] : one_a, lo ? vv[G + 2][1] : one_a, lo ? one_b : vv[G + 2][0], lo ? one_b : vv[G + 2][1]);
                        stsm4(vw + pt * KVP + 4096, vv[G + 3][0], vv[G + 3][1], vv[G + 4][0], vv[G + 4][1]);
                    }
                }
            }
            fence_async_smem();
            mbar_arrive(bar(B_STG + w));
            const float qs = 0.22360679774997896f * 1.4426950408889634f;
            const float rq0 = r0 * qs, rq1 = r1 * qs, m0 = n0 * qs, m1 = n1 * qs;
            uint32_t qg[10][2];
#pragma unroll
            for (int G = 0; G < 10; G++) {
                const float* a = G < 8 ? &acc[4 * G] : &acc2[4 * (G - 8)];
                const float2 cs = lds_f2(sb + OFF_CSQ + (8 * G + 2 * q) * 4);
                qg[G][0] = pack2(fmaf(rq0, a[0], m0 * cs.x), fmaf(rq0, a[1], m0 * cs.y));
                qg[G][1] = pack2(fmaf(rq1, a[2], m1 * cs.x), fmaf(rq1, a[3], m1 * cs.y));
            }
            {
                const uint32_t qw = aring + KVH + (wq * 16 + ((lane >> 3) & 1) * 8 + (lane & 7)) * 160 + (lane >> 4) * 16;
#pragma unroll
                for (int G = 0; G < 10; G += 2) stsm4(qw + G * 16, qg[G][0], qg[G][1], qg[G + 1][0], qg[G + 1][1]);
            }
#pragma unroll
            for (int pt = 0; pt < 2; pt++) {
                const int G = 5 * pt;
                Q[2 * pt][0] = qg[G][0]; Q[2 * pt][1] = qg[G][1]; Q[2 * pt][2] = qg[G + 1][0]; Q[2 * pt][3] = qg[G + 1][1];
                Q[2 * pt][4] = lo ? qg[G + 2][0] : 0u; Q[2 * pt][5] = lo ? qg[G + 2][1] : 0u; Q[2 * pt][6] = 0u; Q[2 * pt][7] = 0u;
                Q[2 * pt + 1][0] = lo ? 0u : qg[G + 2][0]; Q[2 * pt + 1][1] = lo ? 0u : qg[G + 2][1];
                Q[2 * pt + 1][2] = qg[G + 3][0]; Q[2 * pt + 1][3] = qg[G + 3][1];
                Q[2 * pt + 1][4] = qg[G + 4][0]; Q[2 * pt + 1][5] = qg[G + 4][1]; Q[2 * pt + 1][6] = 0u; Q[2 * pt + 1][7] = 0u;
            }
#pragma unroll
            for (int h = 0; h < 4; h++) pin(Q[h]);
            wg_bar(1 + w);
            if (w == 0 && t == 0) mbar_arrive(bar(B_KV0));
        }
        TSW(26 + w * 16);

        {
            float O[4][12], S0[32], S1[32];
            uint32_t P0[16], P1[16];
#pragma unroll
            for (int h = 0; h < 4; h++) zero(O[h]);
            zero(S0); zero(S1);
#pragma unroll
            for (int i = 0; i < 16; i++) { P0[i] = 0; P1[i] = 0; }
            const uint32_t dm = (2 * q <= g8 ? 0xffffu : 0u) | (2 * q + 1 <= g8 ? 0xffff0000u : 0u);
            const uint32_t xfree = mapa(bar(B_XFREE), p ^ 1);
#define ATTPERM 1
            const int perm = ATTPERM && w == 0 && hb >= 4;
            auto dof = [&](int step) -> int { return (step - w) ^ (perm & (step >> 1)); };
            auto release = [&](int step) {
                const int d = dof(step), idx = d == 2 ? -1 : (d & 3) == 0 ? 1 : d - 1;
                mbar_arrive_if(bar(B_ATT + idx), lane == 0 && step != 0 && (unsigned)idx < 3u);
                mbar_arrive_remote_if(xfree, lane == 0 && d == 2);
            };
            auto blk4 = [&](int step) -> uint32_t { const int d = dof(step); return ((sb & 0x3FFFF) + (d == 0 ? OFF_A : kv_slot(d))) >> 4; };
            auto blkbar = [&](int step) -> uint32_t { const int d = dof(step); return bar(d == 0 ? B_KV0 : B_KVFULL + d - 1); };
            auto keybar = [&](int step) -> uint32_t { const int d = dof(step); return bar(d == 0 ? B_KV0 : KSPLIT && d == 1 ? B_KIN : B_KVFULL + d - 1); };
#define RST(k, c)
            uint32_t ma[4];
#pragma unroll
            for (int g = 0; g < 4; g++) ma[g] = g < wq ? ~0u : g == wq ? dm : 0u;
            pin(ma);
            const uint32_t own4 = (aring & 0x3FFFF) >> 4;
            const int iend = min(4, hb + 1);
#define LOP3SEL 1
#define MPOS 3
#define MSYM 1
            const int mpos = MSYM ? min(__shfl_sync(0xffffffffu, opaque(MPOS), 0), iend) : w ? min(MPOS, iend) : iend;
            uint32_t kv4 = own4;
            if (mpos > 1) { kv4 = blk4(1); mbar_wait<16>(keybar(1), 0); }
            qk_issue(S0, Q[0], kv4, 0);
            wg_wait<0>(); pin(S0);
            int i = 1, prev = 0;
            const int e = mpos;
#pragma unroll 1
                for (; i < e; i++) {
                    const bool more = i + 1 < e;
                    const uint32_t nx4 = more ? blk4(i + 1) : own4;
                    RST(0, i == 0); RST(1, i == 1); RST(2, i == 2); RST(3, i == 3); RST(4, i == 4);
                    qk_issue(S1, Q[1], kv4, 1); att_tile<KSPLIT>(S0, P0, O[0], kv4, 0, blkbar(i)); wg_wait<1>(); pin(S1);
                    RST(5, i == TSB); RST(9, i == 2);
                    release(prev);
                    prev = i;
                    qk_issue(S0, Q[2], kv4, 2); att_tile(S1, P1, O[1], kv4, 1); wg_wait<1>(); pin(S0);
                    RST(6, i == TSB); RST(10, i == 2);
                    qk_issue(S1, Q[3], kv4, 3); att_tile(S0, P0, O[2], kv4, 2); wg_wait<1>(); pin(S1);
                    RST(7, i == TSB); RST(11, i == 2);
                    if (more) mbar_wait<16>(keybar(i + 1), 0);
                    RST(8, i == TSB);
                    qk_issue(S0, Q[0], nx4, 0); att_tile(S1, P1, O[3], kv4, 3); wg_wait<1>(); pin(S0);
                    kv4 = nx4;
                }
                {
                    const bool old = hb >= 4, more = i < iend;
                    const uint32_t od4 = old ? blk4(4) : own4, ho = old ? ~0u : 0u, nx4 = more ? blk4(i) : own4;
                    uint32_t cm[3];
#pragma unroll
                    for (int g = 1; g < 4; g++) cm[g - 1] = g <= wq ? ~0u : 0u;
                    pin(cm);
                    auto CM = [&](int g) -> uint32_t { return g <= 0 ? ~0u : g >= 4 ? 0u : cm[g - 1]; };
                    uint32_t hom = ho; asm volatile("" : "+r"(hom));
                    uint32_t fa[4], fb[4];
#pragma unroll
                    for (int g = 0; g < 4; g++) { fa[g] = __byte_perm(ma[g], 0, 0x0000); fb[g] = __byte_perm(ma[g], 0, 0x2222); }
                    pin(fa); pin(fb);
                    if (old) mbar_wait<16>(blkbar(4), 0);
                    qk_issue(S1, Q[0], od4, 0);
                    wg_wait<0>(); pin(S1); pin(P0); pin(P1);
                    release(prev);
#pragma unroll
                    for (int h = 0; h < 4; h++) {
#pragma unroll
                        for (int u = 0; u < 32; u++) {
                            const int g = u >> 3, c = u & 7;
                            const uint32_t dg = (c == 0 || c == 6) ? fa[g] : (c == 1 || c == 7) ? fb[g] : c < 4 ? CM(g) : CM(g + 1);
                            if (g == 0 && (c == 2 || c == 3)) continue;
                            if (g == 3 && (c == 4 || c == 5)) { S0[u] = S1[u]; continue; }
                            asm("lop3.b32 %0, %0, %1, %2, 0xE4;" : "+f"(S0[u]) : "f"(S1[u]), "r"(dg));
                        }
                        pin(S0);
                        if (h < 3) qk_issue(S1, Q[h + 1], od4, h + 1);
#pragma unroll
                        for (int u = 0; u < 16; u++) S0[u] = ex2(S0[u]);
                        if (h > 0) { if (h < 3) wg_wait<1>(); else wg_wait<0>(); pin(P0); pin(P1); pin(S0); }
#pragma unroll
                        for (int u = 16; u < 32; u++) S0[u] = ex2(S0[u]);
#pragma unroll
                        for (int u = 0; u < 16; u++) {
                            const uint32_t pp = pack2(S0[2 * u], S0[2 * u + 1]);
                            const int g = u >> 2;
                            const uint32_t mk = (u & 3) == 1 ? CM(g) : (u & 3) == 2 ? CM(g + 1) : ma[g];
                            P0[u] = pp & mk;
                            asm("lop3.b32 %0, %1, %2, %3, 0x20;" : "=r"(P1[u]) : "r"(pp), "r"(mk), "r"(hom));
                        }
                        if (h == 3 && more) mbar_wait<16>(blkbar(i), 0);
                        qk_issue(S0, Q[(h + 1) & 3], h < 3 ? own4 : nx4, (h + 1) & 3);
                        wg_fence();
#pragma unroll
                        for (int g = 0; g < 4; g++) { pv_one(O[h], P0, own4, h, g); pv_one(O[h], P1, od4, h, g); }
                        wg_commit();
                        if (h < 3) { wg_wait<1>(); pin(S0); pin(S1); }
                    }
                    wg_wait<0>(); pin(S0); pin(S1); pin(P0); pin(P1);
                    release(4);
                    prev = 0;
                    kv4 = nx4;
                }
            if (i < iend) {
                qk_issue(S1, Q[1], kv4, 1); att_tile(S0, P0, O[0], kv4, 0); wg_wait<1>(); pin(S1);
                qk_issue(S0, Q[2], kv4, 2); att_tile(S1, P1, O[1], kv4, 1); wg_wait<1>(); pin(S0);
                qk_issue(S1, Q[3], kv4, 3); att_tile(S0, P0, O[2], kv4, 2); wg_wait<1>(); pin(S1);
                att_tile(S1, P1, O[3], kv4, 3);
                prev = i;
            }
            wg_wait<0>();
#pragma unroll
            for (int h = 0; h < 4; h++) pin(O[h]);
            pin(P0); pin(P1);
            release(prev);
#pragma unroll 1
            for (int s = iend; s <= 3; s++) release(s);
            TSW(27 + w * 16);
            bool ok = true;
            float inv[4][2];
#pragma unroll
            for (int h = 0; h < 4; h++) {
#pragma unroll
                for (int u = 0; u < 2; u++)
                    inv[h][u] = __shfl_sync(0xffffffffu, O[h][((h & 1) ? 0 : 8) + 2 * u], (lane & ~3) | ((h & 1) ? 0 : 2));
            }
#pragma unroll
            for (int h = 0; h < 4; h++) {
#pragma unroll
                for (int u = 0; u < 2; u++) {
                    const float v = inv[h][u];
                    ok = ok & (v >= 8.67e-19f) & (v <= 1.15e18f);
                    asm("rcp.approx.ftz.f32 %0, %1;" : "=f"(inv[h][u]) : "f"(v));
                }
            }
            const bool lo = q < 2;
            uint32_t og[10][2];
#pragma unroll
            for (int pt = 0; pt < 2; pt++) {
                const float* e = O[2 * pt]; const float* o = O[2 * pt + 1];
                const float e0 = inv[2 * pt][0], e1 = inv[2 * pt][1], o0 = inv[2 * pt + 1][0], o1 = inv[2 * pt + 1][1];
                og[5 * pt][0] = pack2(e[0] * e0, e[1] * e0); og[5 * pt][1] = pack2(e[2] * e1, e[3] * e1);
                og[5 * pt + 1][0] = pack2(e[4] * e0, e[5] * e0); og[5 * pt + 1][1] = pack2(e[6] * e1, e[7] * e1);
                og[5 * pt + 2][0] = pack2((lo ? e[8] : o[0]) * (lo ? e0 : o0), (lo ? e[9] : o[1]) * (lo ? e0 : o0));
                og[5 * pt + 2][1] = pack2((lo ? e[10] : o[2]) * (lo ? e1 : o1), (lo ? e[11] : o[3]) * (lo ? e1 : o1));
                og[5 * pt + 3][0] = pack2(o[4] * o0, o[5] * o0); og[5 * pt + 3][1] = pack2(o[6] * o1, o[7] * o1);
                og[5 * pt + 4][0] = pack2(o[8] * o0, o[9] * o0); og[5 * pt + 4][1] = pack2(o[10] * o1, o[11] * o1);
            }
            uint32_t chk[4] = {0, 0, 0, 0};
#pragma unroll
            for (int G = 0; G < 10; G++) {
                asm("fma.rn.bf16x2 %0, %1, %2, %0;" : "+r"(chk[(G & 1) * 2]) : "r"(og[G][0]), "r"(0u));
                asm("fma.rn.bf16x2 %0, %1, %2, %0;" : "+r"(chk[(G & 1) * 2 + 1]) : "r"(og[G][1]), "r"(0u));
            }
            ok = ok & ((chk[0] | chk[1] | chk[2] | chk[3]) == 0);
            mbar_wait<8>(bar(B_KVOUT + w), 0);
            mbar_wait<8>(bar(B_ATT), 0);
            const int rowl = wq * 16 + ((lane >> 3) & 1) * 8 + (lane & 7);
            const uint32_t stq = aring + rowl * 128, stx = lane & 7, sth = lane >> 4;
#pragma unroll
            for (int G = 0; G < 8; G += 2) stsm4(stq + (((G + sth) ^ stx) << 4), og[G][0], og[G][1], og[G + 1][0], og[G + 1][1]);
            stsm4(aring + 8192 + sth * 1024 + rowl * 16, og[8][0], og[8][1], og[9][0], og[9][1]);
            fence_async_smem();
            if (!wg_bar_and(1 + w, ok)) {
                uint8_t* ring = smem + OFF_A + w * 32768;
                attn_fallback(ring, hb, j, (ld_relaxed(&g_done) >> 7) + 1);
                fence_async_smem();
                wg_bar(1 + w);
            }
            mbar_arrive(bar(B_STG + w));
        }
        TSW(28 + w * 16);
        asm volatile("barrier.cluster.wait.aligned;" ::: "memory");

        const int row0 = hb * 64 + wq * 16 + g8;
        uint32_t res[20], bb[10];
#pragma unroll
        for (int G = 0; G < 10; G++) {
            const int col = (G < 8 ? 64 * cown + 8 * G : 512 + 16 * cown + 8 * (G - 8)) + 2 * q;
            res[2 * G] = __ldg(reinterpret_cast<const uint32_t*>(P.x + (size_t)row0 * DM + col));
            res[2 * G + 1] = __ldg(reinterpret_cast<const uint32_t*>(P.x + (size_t)(row0 + 8) * DM + col));
            bb[G] = __ldg(reinterpret_cast<const uint32_t*>(P.b2 + col));
        }
        int bs = 0; uint32_t bph = 0, afb = 0;
#pragma unroll 1
        for (int pass = 0; pass < 2; pass++) {
            if (pass == 1) {
                float acc[96];
                zero(acc);
                float2 hs[4];
#pragma unroll
                for (int i = 0; i < 4; i++) hs[i] = make_float2(0.f, 0.f);
#define EARLYREL 0
                auto step = [&](int k, int k0) {
                    const int s = k & 3;
                    mbar_wait<64>(bar(B_BFULL + bs), bph);
                    if (k > 0) { mbar_wait<128>(bar(B_AFULL + w * 4 + s), (afb >> s) & 1); afb ^= 1u << s; }
                    if (k == 2) TSW(119 + w * 3);
                    if (k == 8) {
                        const uint8_t* hp = g_h + (size_t)(hb * 8 + 2 * (opaque(tid) & 3)) * HREC + 10240 + (wq * 16 + g8) * 8;
                        hs[0] = __ldcg(reinterpret_cast<const float2*>(hp)); hs[1] = __ldcg(reinterpret_cast<const float2*>(hp + HREC));
                        hs[2] = __ldcg(reinterpret_cast<const float2*>(hp + 64)); hs[3] = __ldcg(reinterpret_cast<const float2*>(hp + HREC + 64));
                    }
                    const bool tail = k >= 8;
                    const uint32_t alo = (((aring & 0x3FFFF) + s * 8192) >> 4) + (tail ? 64u << 16 : 1u << 16), ahi = tail ? 8u : 0x40000040u, ast = tail ? 128 : 2;
                    const uint64_t db = mkdesc(sb + bs * BSLOT, 8192, 1024, 1);
                    wg_fence();
#pragma unroll
                    for (int kk = 0; kk < 4; kk++) wgmma_ss_n192_tb(acc, mkd(alo + ast * kk, ahi), db + 128 * kk, 1);
                    wg_commit();
                    wg_wait<1>();
                    if (t == 0 && k > k0) { mbar_arrive(bar(B_BEMPTY + (bs == 0 ? 4 : bs - 1))); mbar_arrive(bar(B_AEMPTY + w * 4 + ((k - 1) & 3))); }
                    if (++bs == 5) { bs = 0; bph ^= 1; }
                };
#pragma unroll 1
                for (int k = 0; k < 10; k++) step(k, 0);
                float s0 = hs[0].x + hs[1].x, q0 = hs[0].y + hs[1].y, s1 = hs[2].x + hs[3].x, q1 = hs[2].y + hs[3].y;
#pragma unroll
                for (int o = 1; o < 4; o <<= 1) {
                    s0 += __shfl_xor_sync(0xffffffffu, s0, o); q0 += __shfl_xor_sync(0xffffffffu, q0, o);
                    s1 += __shfl_xor_sync(0xffffffffu, s1, o); q1 += __shfl_xor_sync(0xffffffffu, q1, o);
                }
                const float mu0 = s0 * (1.f / DM), mu1 = s1 * (1.f / DM);
                const float rs0 = rsqrtf(fmaxf(q0 * (1.f / DM) - mu0 * mu0, 0.f) + 1e-5f), rs1 = rsqrtf(fmaxf(q1 * (1.f / DM) - mu1 * mu1, 0.f) + 1e-5f);
                const float n0 = -mu0 * rs0, n1 = -mu1 * rs1;
                mbar_wait<8>(bar(B_VEC1), 0);
                wg_wait<0>();
                pin(acc);
                if (t == 0) { mbar_arrive(bar(B_BEMPTY + (bs == 0 ? 4 : bs - 1))); mbar_arrive(bar(B_AEMPTY + w * 4 + 1)); }
                TSW(30 + w * 16);
                const int tz = opaque(tid), lz = tz & 31;
                const uint32_t stq = aring + (((tz >> 5) & 3) * 16 + ((lz >> 3) & 1) * 8 + (lz & 7)) * 128;
                const uint32_t stx = (lz & 7), sth = lz >> 4, vq = sb + OFF_V1 + (lz & 3) * 16;
                float4 v[8];
#pragma unroll
                for (int G = 0; G < 8; G++) v[G] = lds_f4(vq + G * 64);
#pragma unroll
                for (int tl = 0; tl < 3; tl++) {
                    uint32_t rr[16];
#pragma unroll
                    for (int G = 0; G < 8; G++) {
                        const float* a = &acc[32 * tl + 4 * G];
                        rr[2 * G] = sq_bf16x2(pack2_relu(fmaf(rs0, a[0], fmaf(n0, v[G].x, v[G].z)), fmaf(rs0, a[1], fmaf(n0, v[G].y, v[G].w))));
                        rr[2 * G + 1] = sq_bf16x2(pack2_relu(fmaf(rs1, a[2], fmaf(n1, v[G].x, v[G].z)), fmaf(rs1, a[3], fmaf(n1, v[G].y, v[G].w))));
                    }
                    if (tl < 2) {
#pragma unroll
                        for (int G = 0; G < 8; G++) v[G] = lds_f4(vq + (8 * tl + 8 + G) * 64);
                    }
#pragma unroll
                    for (int G = 0; G < 8; G += 2) stsm4(stq + tl * 8192 + (((G + sth) ^ stx) << 4), rr[2 * G], rr[2 * G + 1], rr[2 * G + 2], rr[2 * G + 3]);
                    if (tl < 2) { fence_async_smem(); mbar_arrive(bar(B_H1T + 2 * tl + w)); }
                }
                fence_async_smem();
                mbar_arrive(bar(B_STG + w));
                wg_bar(1 + w);
                TSW(31 + w * 16);
            }
            float acc[80];
#pragma unroll
            for (int G = 0; G < 10; G++) {
                const uint32_t bv = pass ? bb[G] : 0u;
                const float v0 = bf_lo(res[2 * G]) + bf_lo(bv), v1 = bf_hi(res[2 * G]) + bf_hi(bv);
                const float v2 = bf_lo(res[2 * G + 1]) + bf_lo(bv), v3 = bf_hi(res[2 * G + 1]) + bf_hi(bv);
                if (G < 8) { acc[4 * G] = v0; acc[4 * G + 1] = v1; acc[4 * G + 2] = v2; acc[4 * G + 3] = v3; acc[32 + 4 * G] = 0.f; acc[33 + 4 * G] = 0.f; acc[34 + 4 * G] = 0.f; acc[35 + 4 * G] = 0.f; }
                else {
                    const int a = 64 + 4 * (G - 8);
                    acc[a] = p ? 0.f : v0; acc[a + 1] = p ? 0.f : v1; acc[a + 2] = p ? 0.f : v2; acc[a + 3] = p ? 0.f : v3;
                    acc[a + 8] = p ? v0 : 0.f; acc[a + 9] = p ? v1 : 0.f; acc[a + 10] = p ? v2 : 0.f; acc[a + 11] = p ? v3 : 0.f;
                }
            }
            const int nk = pass ? 12 : 5, nloc = pass ? 3 : 1;
#pragma unroll 1
            for (int k = 0; k < nk; k++) {
                const int s = k & 3;
                mbar_wait<64>(bar(B_BFULL + bs), bph);
                if (k >= nloc) { mbar_wait<128>(bar(B_AFULL + w * 4 + s), (afb >> s) & 1); afb ^= 1u << s; }
                if (k == nloc) TSW(118 + w * 3 + 2 * pass);
                const bool tail = pass == 0 && k == 4;
                const uint32_t alo = (((aring & 0x3FFFF) + s * 8192) >> 4) + (tail ? 64u << 16 : 1u << 16), ahi = tail ? 8u : 0x40000040u, ast = tail ? 128 : 2;
                const uint64_t db = mkdesc(sb + bs * BSLOT, 8192, 1024, 1);
                wg_fence();
#pragma unroll
                for (int kk = 0; kk < 4; kk++) wgmma_ss_n160_tb(acc, mkd(alo + ast * kk, ahi), db + 128 * kk, 1);
                wg_commit();
                wg_wait<1>();
                if (t == 0 && k > 0) { mbar_arrive(bar(B_BEMPTY + (bs == 0 ? 4 : bs - 1))); mbar_arrive(bar(B_AEMPTY + w * 4 + ((k - 1) & 3))); }
                if (++bs == 5) { bs = 0; bph ^= 1; }
            }
            if (t == 0) mbar_expect_tx(bar(B_RECV + w), RECV_BYTES);
            if (pass == 0) mbar_wait<8>(bar(B_XFREE), 0);
            wg_wait<0>();
            pin(acc);
            if (t == 0) { mbar_arrive(bar(B_BEMPTY + (bs == 0 ? 4 : bs - 1))); mbar_arrive(bar(B_AEMPTY + w * 4 + ((nk - 1) & 3))); }
            TSW(pass ? 32 + w * 16 : 29 + w * 16);
            const int tz = opaque(tid), lz = tz & 31, tt = tz & 127, rowz = ((tz >> 5) & 3) * 16 + ((lz >> 3) & 1) * 8 + (lz & 7);
            const uint32_t stq = aring + rowz * 128;
            const uint32_t stx = (lz & 7), sth = lz >> 4;
            float keep[40];
            {
                float snd[40];
#pragma unroll
                for (int i = 0; i < 32; i++) { keep[i] = acc[i]; snd[i] = acc[32 + i]; }
#pragma unroll
                for (int i = 0; i < 8; i++) { keep[32 + i] = p ? acc[72 + i] : acc[64 + i]; snd[32 + i] = p ? acc[64 + i] : acc[72 + i]; }
                const uint32_t rbar = mapa(bar(B_RECV + w), p ^ 1);
                const uint32_t rdst = mapa(sb + OFF_X + w * 20480 + tt * 16, p ^ 1);
#pragma unroll
                for (int i = 0; i < 5; i++)
                    asm volatile("st.async.weak.shared::cluster.mbarrier::complete_tx::bytes.v4.b32 [%0], {%1, %2, %3, %4}, [%5];"
                        :: "r"(rdst + i * 2048), "r"(pack2(snd[8 * i], snd[8 * i + 1])), "r"(pack2(snd[8 * i + 2], snd[8 * i + 3])),
                           "r"(pack2(snd[8 * i + 4], snd[8 * i + 5])), "r"(pack2(snd[8 * i + 6], snd[8 * i + 7])), "r"(rbar) : "memory");
            }
            mbar_wait<8>(bar(B_RECV + w), pass);
            const uint32_t rsrc = sb + OFF_X + w * 20480 + tt * 16;
#pragma unroll
            for (int i = 0; i < 5; i++) {
                uint4 v; asm volatile("ld.shared.v4.b32 {%0, %1, %2, %3}, [%4];" : "=r"(v.x), "=r"(v.y), "=r"(v.z), "=r"(v.w) : "r"(rsrc + i * 2048));
                keep[8 * i] += bf_lo(v.x); keep[8 * i + 1] += bf_hi(v.x); keep[8 * i + 2] += bf_lo(v.y); keep[8 * i + 3] += bf_hi(v.y);
                keep[8 * i + 4] += bf_lo(v.z); keep[8 * i + 5] += bf_hi(v.z); keep[8 * i + 6] += bf_lo(v.w); keep[8 * i + 7] += bf_hi(v.w);
            }
#pragma unroll
            for (int G = 0; G < 10; G++) { res[2 * G] = pack2(keep[4 * G], keep[4 * G + 1]); res[2 * G + 1] = pack2(keep[4 * G + 2], keep[4 * G + 3]); }
#pragma unroll
            for (int G = 0; G < 8; G += 2)
                stsm4(stq + (((G + sth) ^ stx) << 4), res[2 * G], res[2 * G + 1], res[2 * G + 2], res[2 * G + 3]);
            stsm4(aring + (pass ? 8192 + rowz * 32 + sth * 16 : 24576 + sth * 1024 + rowz * 16), res[16], res[17], res[18], res[19]);
            if (HSTG) { fence_async_smem(); mbar_arrive(bar(B_STG + w)); }
            if (pass == 0) {
                float s0 = 0.f, q0 = 0.f, s1 = 0.f, q1 = 0.f;
#pragma unroll
                for (int G = 0; G < 10; G++) {
                    const float a = bf_lo(res[2 * G]), c = bf_hi(res[2 * G]), d = bf_lo(res[2 * G + 1]), e = bf_hi(res[2 * G + 1]);
                    s0 += a + c; q0 += a * a + c * c; s1 += d + e; q1 += d * d + e * e;
                }
#pragma unroll
                for (int o = 1; o < 4; o <<= 1) {
                    s0 += __shfl_xor_sync(0xffffffffu, s0, o); q0 += __shfl_xor_sync(0xffffffffu, q0, o);
                    s1 += __shfl_xor_sync(0xffffffffu, s1, o); q1 += __shfl_xor_sync(0xffffffffu, q1, o);
                }
                if ((lz & 3) == 0) {
                    float2* hp = reinterpret_cast<float2*>(HSTG ? g_h + (size_t)(hb * 8 + cown) * HREC + 10240 : smem + OFF_A + w * 32768 + 26624) + ((tz >> 5) & 3) * 16 + (lz >> 2);
                    if (HSTG) { __stcg(hp, make_float2(s0, q0)); __stcg(hp + 8, make_float2(s1, q1)); }
                    else { hp[0] = make_float2(s0, q0); hp[8] = make_float2(s1, q1); }
                }
            }
            if (!HSTG) { fence_async_smem(); mbar_arrive(bar(B_STG + w)); }
            if (pass == 0) {
                wg_bar(1 + w);
                if (HSTG && (tz & 127) == 0) mbar_arrive(bar(w ? B_GO : B_D1));
            }
            TSW(pass ? 33 + w * 16 : 34 + w * 16);
        }
    }
}

typedef CUresult (*EncodeFn)(CUtensorMap*, CUtensorMapDataType, cuuint32_t, void*, const cuuint64_t*, const cuuint64_t*, const cuuint32_t*, const cuuint32_t*,
                             CUtensorMapInterleave, CUtensorMapSwizzle, CUtensorMapL2promotion, CUtensorMapFloatOOBfill);

void encode2d(EncodeFn enc, CUtensorMap* m, const void* base, int rows, int cols, int boxc, int boxr, CUtensorMapSwizzle sw) {
    cuuint64_t gd[2] = {(cuuint64_t)cols, (cuuint64_t)rows};
    cuuint64_t gs[1] = {(cuuint64_t)cols * 2};
    cuuint32_t bd[2] = {(cuuint32_t)boxc, (cuuint32_t)boxr};
    cuuint32_t es[2] = {1, 1};
    enc(m, CU_TENSOR_MAP_DATA_TYPE_BFLOAT16, 2, const_cast<void*>(base), gd, gs, bd, es, CU_TENSOR_MAP_INTERLEAVE_NONE, sw,
        CU_TENSOR_MAP_L2_PROMOTION_L2_128B, CU_TENSOR_MAP_FLOAT_OOB_FILL_NONE);
}
void encode3d(EncodeFn enc, CUtensorMap* m, const void* base, int d0, int d1, int d2, size_t s1, size_t s2, int b0, int b1, int b2, CUtensorMapSwizzle sw) {
    cuuint64_t gd[3] = {(cuuint64_t)d0, (cuuint64_t)d1, (cuuint64_t)d2}; cuuint64_t gs[2] = {s1, s2};
    cuuint32_t bd[3] = {(cuuint32_t)b0, (cuuint32_t)b1, (cuuint32_t)b2}; cuuint32_t es[3] = {1, 1, 1};
    enc(m, CU_TENSOR_MAP_DATA_TYPE_BFLOAT16, 3, const_cast<void*>(base), gd, gs, bd, es, CU_TENSOR_MAP_INTERLEAVE_NONE, sw,
        CU_TENSOR_MAP_L2_PROMOTION_L2_128B, CU_TENSOR_MAP_FLOAT_OOB_FILL_NONE);
}

}

extern "C" void kernel_launch(void* const* d_in, const int* in_sizes, int n_in, void* d_out, int out_size) {
    (void)in_sizes; (void)n_in; (void)out_size;
    static EncodeFn enc = nullptr;
    if (!enc) {
        void* f = nullptr; cudaDriverEntryPointQueryResult qr;
        cudaGetDriverEntryPoint("cuTensorMapEncodeTiled", &f, cudaEnableDefault, &qr);
        enc = (EncodeFn)f;
        cudaFuncSetAttribute(fused_block_kernel, cudaFuncAttributeMaxDynamicSharedMemorySize, SMEM_BYTES);
    }
    Params P;
    const __nv_bfloat16* wqkv = (const __nv_bfloat16*)d_in[1];
    const __nv_bfloat16* w1 = (const __nv_bfloat16*)d_in[4];
    P.x = (const __nv_bfloat16*)d_in[0]; P.wo = (const __nv_bfloat16*)d_in[2];
    P.b1 = (const __nv_bfloat16*)d_in[5]; P.w2 = (const __nv_bfloat16*)d_in[6]; P.b2 = (const __nv_bfloat16*)d_in[7];
    const CUtensorMapSwizzle S128 = CU_TENSOR_MAP_SWIZZLE_128B, SN = CU_TENSOR_MAP_SWIZZLE_NONE;
    encode2d(enc, &P.mX, P.x, SEQ, DM, 64, 64, S128);
    encode3d(enc, &P.mWq, wqkv, 640, 640, 3, 3840, 1280, 64, 64, 3, S128);
    encode3d(enc, &P.mWqC, wqkv, 640, 640, 3, 3840, 1280, 16, 64, 3, CU_TENSOR_MAP_SWIZZLE_32B);
    encode2d(enc, &P.mWqS, wqkv, DM, 3 * DM, 16, 128, SN);
    encode2d(enc, &P.mW1S, w1, DM, FF, 16, 128, SN);
    encode2d(enc, &P.mWo, P.wo, DM, DM, 64, 64, S128);
    encode2d(enc, &P.mWoH, P.wo, DM, DM, 32, 64, S128);
    encode3d(enc, &P.mWoT, P.wo, 640, 80, 8, 1280, 80 * 1280, 64, 16, 4, S128);
    encode3d(enc, &P.mWoTH, P.wo, 640, 80, 8, 1280, 80 * 1280, 32, 16, 4, S128);
    encode2d(enc, &P.mW1, w1, DM, FF, 64, 64, S128);
    encode2d(enc, &P.mW2, P.w2, FF, DM, 64, 64, S128);
    encode2d(enc, &P.mW2H, P.w2, FF, DM, 32, 64, S128);
    encode2d(enc, &P.mOut, d_out, SEQ, DM, 64, 64, S128);
    encode2d(enc, &P.mOutT, d_out, SEQ, DM, 16, 64, SN);
    fused_block_kernel<<<128, 384, SMEM_BYTES, cudaStreamPerThread>>>(P);
}
```
